```python
import torch

def _softmax(x, axis=-1):
    return torch.softmax(x, dim=axis)
def _gelu(x):
    return torch.nn.functional.gelu(x, approximate="tanh")
def _silu(x):
    return torch.nn.functional.silu(x)
def _sigmoid(x):
    return torch.sigmoid(x)
def _layernorm(x, axis=-1, eps=1e-5):
    m = x.mean(dim=axis, keepdim=True)
    v = x.var(dim=axis, keepdim=True, unbiased=False)
    return (x - m) / torch.sqrt(v + eps)
def _scatter_add(tgt, idx, src, axis=0):
    return tgt.clone().index_add_(axis, idx, src)
def _segment_sum(src, seg, n):
    out = torch.zeros((n,) + src.shape[1:], dtype=src.dtype)
    return out.index_add_(0, seg, src)
def _pad(x, pw):
    flat = tuple(v for pair in reversed(pw) for v in pair)
    return torch.nn.functional.pad(x, flat)

kernel_name = 'concat_heads__grouped_kv_mqa__linear_attn_block__prompt'

def setup_inputs():

    _w = (lambda a: (lambda t: t.to(torch.bfloat16) if t.is_floating_point() else t)(torch.as_tensor(a)))
    def _A_setup():
        B, S, D, H = 1, 2048, 512, 32
        Dh = D // H
        return {
            "x": _w((lambda *s: torch.randn(*s, dtype=torch.bfloat16) * 0.05)(B, S, D)),
            "wq": _w((lambda *s: torch.randn(*s, dtype=torch.bfloat16) * 1.6)(D, H * Dh)),
            "wk": _w((lambda *s: torch.randn(*s, dtype=torch.bfloat16) * 1.6)(D, Dh)),
            "wv": _w((lambda *s: torch.randn(*s, dtype=torch.bfloat16) * 0.05)(D, Dh)),
            "wo": _w((lambda *s: torch.randn(*s, dtype=torch.bfloat16) * 0.05)(H * Dh, D)),
        }
    _A_in = _A_setup()

    def _B_setup():
        B, S, D = 1, 2048, 512
        return {
            "x": _w((lambda *s: torch.randn(*s, dtype=torch.bfloat16) * 0.05)(B, S, D)),
            "wqkv": _w((lambda *s: torch.randn(*s, dtype=torch.bfloat16) * 0.8)(D, 3 * D)),
            "wo": _w((lambda *s: torch.randn(*s, dtype=torch.bfloat16) * 0.05)(D, D)),
        }
    _B_in = _B_setup()

    return {
        "A_x": _A_in["x"],
        "A_wq": _A_in["wq"],
        "A_wk": _A_in["wk"],
        "A_wv": _A_in["wv"],
        "A_wo": _A_in["wo"],
        "B_x": _B_in["x"],
        "B_wqkv": _B_in["wqkv"],
        "B_wo": _B_in["wo"],
    }

def reference(A_x, A_wq, A_wk, A_wv, A_wo, B_x, B_wqkv, B_wo):
    def _A_ref(x, wq, wk, wv, wo):
        B, S, D = x.shape
        H = 32
        Dh = D // H
        q = (lambda x, *d: x.permute(*d))((x @ wq).reshape(B, S, H, Dh), 0, 2, 1, 3)
        k = x @ wk
        v = x @ wv
        scores = torch.einsum("bhqd,bkd->bhqk", q, k) * (Dh ** -0.5)
        p = _softmax(scores, axis=-1)
        o = torch.einsum("bhqk,bkd->bhqd", p, v)
        return (lambda x, *d: x.permute(*d))(o, 0, 2, 1, 3).reshape(B, S, H * Dh) @ wo

    def _B_ref(x, wqkv, wo):
        B, S, D = x.shape
        H = 32; Dh = D // H
        qkv = (lambda x, *d: x.permute(*d))((x @ wqkv).reshape(B, S, 3, H, Dh), 2, 0, 3, 1, 4)
        q, k, v = qkv[0], qkv[1], qkv[2]
        phi = lambda t: torch.where(t > 0, t + 1, torch.exp(t)) + 1e-6
        pq, pk = phi(q), phi(k)
        kv = torch.einsum("bhsd,bhse->bhde", pk, v)
        z = torch.einsum("bhsd->bhd", pk)
        num = torch.einsum("bhqd,bhde->bhqe", pq, kv)
        den = torch.einsum("bhqd,bhd->bhq", pq, z)[..., None] + 1e-6
        o = num / den
        return (lambda x, *d: x.permute(*d))(o, 0, 2, 1, 3).reshape(B, S, D) @ wo

    a = _A_ref(A_x, A_wq, A_wk, A_wv, A_wo)
    b = _B_ref(B_x, B_wqkv, B_wo)
    return torch.concatenate([a, b], axis=-1)
```

```cpp
#include <cuda_runtime.h>
#include <cuda_bf16.h>
#include <cuda_fp16.h>
#include <cuda.h>
#include <stdint.h>

namespace {

constexpr int NCTA = 128;
constexpr int NTHREADS = 640;

constexpr uint32_t TILE_BYTES = 5120;
constexpr uint32_t CHUNK_BYTES = 4 * TILE_BYTES;
constexpr uint32_t KV_BYTES = 32 * TILE_BYTES;
constexpr uint32_t SM_KV = 0;
constexpr uint32_t SM_WKV = 0;
constexpr uint32_t SM_KSCR = 16384;
constexpr uint32_t SM_QX = 20480;
constexpr uint32_t SM_WQ0 = 32768;
constexpr uint32_t SM_XA = 98304;
constexpr uint32_t SM_T1A = 0;
constexpr uint32_t SM_T0A = 32768;
constexpr uint32_t SM_T0W = 65536;
constexpr uint32_t SM_TO = 131072;
constexpr uint32_t SM_AUX = KV_BYTES;
constexpr uint32_t STAGE_BYTES = 24576;
constexpr uint32_t SM_X = SM_AUX + 2 * STAGE_BYTES;
constexpr uint32_t SM_BAR = SM_X + 16384;
constexpr uint32_t SM_KMAX = SM_BAR + 512;
constexpr uint32_t SM_MISC = SM_KMAX + 512;
constexpr uint32_t SM_TOTAL = SM_MISC + 64;
constexpr uint32_t SB = 1024;
constexpr uint32_t BAR = SB + SM_BAR;
constexpr int B_X = 0, B_W0 = 8  , B_KV = 12, B_TW = 15, B_EP = 16, B_KS = 17, B_PC = 18, B_KM = 19, B_T0 = 20,
              B_FULL = 21,
              B_KP = 23, B_KR = 24, B_QP = 25, B_Q1 = 26, B_F3 = 27,
              B_QD = 28, B_OD = 29, B_HF = 30, B_TA = 31, B_END = 35;

constexpr uint32_t MUFU_MASK = 0x5308u;
__host__ __device__ constexpr bool pair_mufu(int i) { return ((MUFU_MASK >> i) & 1u) != 0; }
__host__ __device__ constexpr bool tile_unit(int j) { return ((MUFU_MASK >> (2 * j)) & 3u) != 0; }

constexpr float QSCALE = 0.25f * 1.4426950408889634f;
constexpr float WIN = 88.0f;
constexpr float GUARD = 150.0f;
constexpr float MUFU_BIAS = WIN - 127.0f + 1.58f;

struct Maps { CUtensorMap xA, wq, woA, xB, wB, woB, oA, oB, out; const uint8_t *pxA, *pwk, *pwv, *pxB, *pwB, *pwoA, *pwoB; };

__device__ __align__(1024) uint8_t g_kv[KV_BYTES];
__device__ __align__(128) float g_kmax[128];
__device__ __align__(128) __nv_bfloat16 g_kabs[2048 * 16];
__device__ __align__(1024) __nv_bfloat16 g_oA[2048 * 512];
__device__ __align__(1024) __nv_bfloat16 g_oB[2048 * 512];
__device__ __align__(128) uint4 g_q[NCTA * 2 * 512];
__device__ __align__(128) float g_kvsum[2][32 * 272];
__device__ __align__(128) uint4 g_llo[NCTA * 512];
__device__ __align__(128) float g_spark[32 * NCTA * 512];
__device__ __align__(128) unsigned g_ticket[32];
__device__ __align__(128) unsigned g_cntKV[64];
__device__ __align__(128) unsigned g_cntKVB[4 * 32];
__device__ __align__(128) unsigned g_cntOB[NCTA * 8];
__device__ __align__(128) unsigned g_cntOA[NCTA * 8];

__device__ __forceinline__ void mbar_init(uint32_t a, int c) { asm volatile("mbarrier.init.shared::cta.b64 [%0],%1;" ::"r"(a), "r"(c) : "memory"); }
__device__ __forceinline__ void mbar_expect(uint32_t a, uint32_t b) { asm volatile("mbarrier.arrive.expect_tx.shared::cta.b64 _,[%0],%1;" ::"r"(a), "r"(b) : "memory"); }
__device__ __forceinline__ void mbar_arrive(uint32_t a) { asm volatile("mbarrier.arrive.shared::cta.b64 _,[%0];" ::"r"(a) : "memory"); }
__device__ __forceinline__ void mbar_wait(uint32_t a, uint32_t ph) {
    asm volatile("{.reg .pred p; .reg .b32 c; mov.b32 c, 0;\n"
                 "L: mbarrier.try_wait.parity.shared::cta.b64 p,[%0],%1; @p bra.uni D;\n"
                 "add.u32 c, c, 1; setp.lt.u32 p, c, 0x1000000; @p bra.uni L; trap;\n"
                 "D: }" ::"r"(a), "r"(ph) : "memory");
}
__device__ __forceinline__ bool mbar_test(uint32_t a, uint32_t ph) {
    uint32_t ok;
    asm volatile("{.reg .pred p; mbarrier.test_wait.parity.shared::cta.b64 p,[%1],%2; selp.b32 %0,1,0,p;}" : "=r"(ok) : "r"(a), "r"(ph) : "memory");
    return ok != 0;
}
__device__ __forceinline__ bool elect() {
    uint32_t ok;
    asm volatile("{.reg .pred p; elect.sync _|p, 0xffffffff; selp.b32 %0,1,0,p;}" : "=r"(ok));
    return ok != 0;
}
__device__ __forceinline__ void fence_async_s() { asm volatile("fence.proxy.async.shared::cta;" ::: "memory"); }
__device__ __forceinline__ void fence_async_g() { asm volatile("fence.proxy.async.global;" ::: "memory"); }
__device__ __forceinline__ void bar_sync(int id, int n) { asm volatile("bar.sync %0,%1;" ::"r"(id), "r"(n) : "memory"); }
__device__ __forceinline__ void bulk_load(uint32_t dst, const void* src, uint32_t n, uint32_t bar) {
    asm volatile("cp.async.bulk.shared::cluster.global.mbarrier::complete_tx::bytes [%0],[%1],%2,[%3];" ::"r"(dst), "l"(src), "r"(n), "r"(bar) : "memory");
}
__device__ __forceinline__ void tma2(uint32_t dst, const CUtensorMap* m, int c0, int c1, uint32_t bar) {
    asm volatile("cp.async.bulk.tensor.2d.shared::cluster.global.tile.mbarrier::complete_tx::bytes [%0],[%1,{%3,%4}],[%2];" ::"r"(dst), "l"(m), "r"(bar), "r"(c0), "r"(c1) : "memory");
}
__device__ __forceinline__ void tma3(uint32_t dst, const CUtensorMap* m, int c0, int c1, int c2, uint32_t bar) {
    asm volatile("cp.async.bulk.tensor.3d.shared::cluster.global.tile.mbarrier::complete_tx::bytes [%0],[%1,{%3,%4,%5}],[%2];" ::"r"(dst), "l"(m), "r"(bar), "r"(c0), "r"(c1), "r"(c2) : "memory");
}
__device__ __forceinline__ void tma3_store(const CUtensorMap* m, int c0, int c1, int c2, uint32_t src) {
    asm volatile("cp.async.bulk.tensor.3d.global.shared::cta.tile.bulk_group [%0,{%2,%3,%4}],[%1];" ::"l"(m), "r"(src), "r"(c0), "r"(c1), "r"(c2) : "memory");
    asm volatile("cp.async.bulk.commit_group;" ::: "memory");
}
__device__ __forceinline__ void tma2_store(const CUtensorMap* m, int c0, int c1, uint32_t src) {
    asm volatile("cp.async.bulk.tensor.2d.global.shared::cta.tile.bulk_group [%0,{%2,%3}],[%1];" ::"l"(m), "r"(src), "r"(c0), "r"(c1) : "memory");
    asm volatile("cp.async.bulk.commit_group;" ::: "memory");
}
__device__ __forceinline__ void bulk_wait_all() { asm volatile("cp.async.bulk.wait_group 0;" ::: "memory"); }
__device__ __forceinline__ void l2_prefetch(const void* p, uint32_t n) { asm volatile("cp.async.bulk.prefetch.L2.global [%0],%1;" ::"l"(p), "r"(n) : "memory"); }
__device__ __forceinline__ void stmatrix4(uint32_t a, uint32_t r0, uint32_t r1, uint32_t r2, uint32_t r3) {
    asm volatile("stmatrix.sync.aligned.m8n8.x4.shared.b16 [%0],{%1,%2,%3,%4};" ::"r"(a), "r"(r0), "r"(r1), "r"(r2), "r"(r3) : "memory");
}
__device__ __forceinline__ float rcp(float x) { float y; asm("rcp.approx.ftz.f32 %0,%1;" : "=f"(y) : "f"(x)); return y; }
__device__ __forceinline__ void red_release(unsigned* p) { asm volatile("red.release.gpu.global.add.u32 [%0],1;" ::"l"(p) : "memory"); }
template <int NS> __device__ __forceinline__ void poll_ge(const unsigned* p, unsigned target) {
    asm volatile("{.reg .pred p; .reg .b32 c, d;\n"
                 "mov.u32 c, %%clock;\n"
                 "L: ld.acquire.gpu.global.u32 d,[%0]; sub.u32 d, d, %1; setp.ge.s32 p, d, 0; @p bra D;\n"
                 "nanosleep.u32 %2;\n"
                 "mov.u32 d, %%clock; sub.u32 d, d, c; setp.lt.u32 p, d, 0x40000000; @p bra L; trap;\n"
                 "D: }" ::"l"(p), "r"(target), "n"(NS) : "memory");
}
__device__ __forceinline__ void ll_store(uint4* p, uint4 v) {
    asm volatile("st.relaxed.gpu.global.v4.u32 [%0],{%1,%2,%3,%4};" ::"l"(p), "r"(~v.x), "r"(~v.y), "r"(~v.z), "r"(~v.w) : "memory");
}
__device__ __forceinline__ uint4 ll_load(const uint4* p) {
    uint4 v;
    asm volatile("ld.relaxed.gpu.global.v4.u32 {%0,%1,%2,%3},[%4];" : "=r"(v.x), "=r"(v.y), "=r"(v.z), "=r"(v.w) : "l"(p) : "memory");
    return v;
}
__device__ __forceinline__ bool ll_empty(uint4 v) { return v.x == 0 || v.y == 0 || v.z == 0 || v.w == 0; }
__device__ __forceinline__ void wg_fence() { asm volatile("wgmma.fence.sync.aligned;" ::: "memory"); }
__device__ __forceinline__ void wg_commit() { asm volatile("wgmma.commit_group.sync.aligned;" ::: "memory"); }
__device__ __forceinline__ void wg_wait0() { asm volatile("wgmma.wait_group.sync.aligned 0;" ::: "memory"); }
template <int N> __device__ __forceinline__ void pin(float (&d)[N]) {
#pragma unroll
    for (int i = 0; i < N; i++) asm volatile("" : "+f"(d[i])::"memory");
}
template <int N> __device__ __forceinline__ void fresh(float (&d)[N]) {
#pragma unroll
    for (int i = 0; i < N; i++) asm volatile("" : "=f"(d[i])::"memory");
}
template <int N> __device__ __forceinline__ void pin(uint32_t (&d)[N]) {
#pragma unroll
    for (int i = 0; i < N; i++) asm volatile("" : "+r"(d[i])::"memory");
}
__device__ __forceinline__ uint64_t mkdesc(uint32_t addr, uint32_t lbo, uint32_t sbo, uint32_t swz) {
    return (uint64_t)((addr & 0x3FFFF) >> 4) | ((uint64_t)(lbo >> 4) << 16) | ((uint64_t)(sbo >> 4) << 32) | ((uint64_t)swz << 62);
}
template <int SD> __device__ __forceinline__ void wg_qk_n64(float (&d)[32], const uint32_t (&a)[4], uint64_t db) {
    asm volatile("{.reg .pred p; setp.ne.b32 p, %37, 0;\n"
        "wgmma.mma_async.sync.aligned.m64n64k16.f32.f16.f16 {%0,%1,%2,%3,%4,%5,%6,%7,%8,%9,%10,%11,%12,%13,%14,%15,%16,%17,%18,%19,%20,%21,%22,%23,%24,%25,%26,%27,%28,%29,%30,%31},{%32,%33,%34,%35},%36,p,1,1,0;}"
        : "+f"(d[0]), "+f"(d[1]), "+f"(d[2]), "+f"(d[3]), "+f"(d[4]), "+f"(d[5]), "+f"(d[6]), "+f"(d[7]), "+f"(d[8]), "+f"(d[9]), "+f"(d[10]), "+f"(d[11]), "+f"(d[12]), "+f"(d[13]), "+f"(d[14]), "+f"(d[15]), "+f"(d[16]), "+f"(d[17]), "+f"(d[18]), "+f"(d[19]), "+f"(d[20]), "+f"(d[21]), "+f"(d[22]), "+f"(d[23]), "+f"(d[24]), "+f"(d[25]), "+f"(d[26]), "+f"(d[27]), "+f"(d[28]), "+f"(d[29]), "+f"(d[30]), "+f"(d[31])
        : "r"(a[0]), "r"(a[1]), "r"(a[2]), "r"(a[3]), "l"(db), "n"(SD));
}
template <int SD> __device__ __forceinline__ void wg_qk_n8(float (&d)[4], const uint32_t (&a)[4], uint64_t db) {
    asm volatile("{.reg .pred p; setp.ne.b32 p, %9, 0;\n"
        "wgmma.mma_async.sync.aligned.m64n8k16.f32.f16.f16 {%0,%1,%2,%3},{%4,%5,%6,%7},%8,p,1,1,0;}"
        : "+f"(d[0]), "+f"(d[1]), "+f"(d[2]), "+f"(d[3])
        : "r"(a[0]), "r"(a[1]), "r"(a[2]), "r"(a[3]), "l"(db), "n"(SD));
}
template <int SD> __device__ __forceinline__ void wg_pv_n24(float (&d)[12], const uint32_t (&a)[4], uint64_t db) {
    asm volatile("{.reg .pred p; setp.ne.b32 p, %17, 0;\n"
        "wgmma.mma_async.sync.aligned.m64n24k16.f32.bf16.bf16 {%0,%1,%2,%3,%4,%5,%6,%7,%8,%9,%10,%11},{%12,%13,%14,%15},%16,p,1,1,1;}"
        : "+f"(d[0]), "+f"(d[1]), "+f"(d[2]), "+f"(d[3]), "+f"(d[4]), "+f"(d[5]), "+f"(d[6]), "+f"(d[7]), "+f"(d[8]), "+f"(d[9]), "+f"(d[10]), "+f"(d[11])
        : "r"(a[0]), "r"(a[1]), "r"(a[2]), "r"(a[3]), "l"(db), "n"(SD));
}
__device__ __forceinline__ void wg_ss_n8(float (&d)[4], uint64_t da, uint64_t db, int sd) {
    asm volatile("{.reg .pred p; setp.ne.b32 p, %6, 0;\n"
        "wgmma.mma_async.sync.aligned.m64n8k16.f32.bf16.bf16 {%0,%1,%2,%3},%4,%5,p,1,1,0,1;}"
        : "+f"(d[0]), "+f"(d[1]), "+f"(d[2]), "+f"(d[3])
        : "l"(da), "l"(db), "r"(sd));
}
__device__ __forceinline__ void wg_ss_n16(float (&d)[8], uint64_t da, uint64_t db, int sd) {
    asm volatile("{.reg .pred p; setp.ne.b32 p, %10, 0;\n"
        "wgmma.mma_async.sync.aligned.m64n16k16.f32.bf16.bf16 {%0,%1,%2,%3,%4,%5,%6,%7},%8,%9,p,1,1,0,1;}"
        : "+f"(d[0]), "+f"(d[1]), "+f"(d[2]), "+f"(d[3]), "+f"(d[4]), "+f"(d[5]), "+f"(d[6]), "+f"(d[7])
        : "l"(da), "l"(db), "r"(sd));
}
__device__ __forceinline__ void wg_ss_n128(float (&d)[64], uint64_t da, uint64_t db, int sd) {
    asm volatile("{.reg .pred p; setp.ne.b32 p, %66, 0;\n"
        "wgmma.mma_async.sync.aligned.m64n128k16.f32.bf16.bf16 {%0,%1,%2,%3,%4,%5,%6,%7,%8,%9,%10,%11,%12,%13,%14,%15,%16,%17,%18,%19,%20,%21,%22,%23,%24,%25,%26,%27,%28,%29,%30,%31,%32,%33,%34,%35,%36,%37,%38,%39,%40,%41,%42,%43,%44,%45,%46,%47,%48,%49,%50,%51,%52,%53,%54,%55,%56,%57,%58,%59,%60,%61,%62,%63},%64,%65,p,1,1,0,1;}"
        : "+f"(d[0]), "+f"(d[1]), "+f"(d[2]), "+f"(d[3]), "+f"(d[4]), "+f"(d[5]), "+f"(d[6]), "+f"(d[7]), "+f"(d[8]), "+f"(d[9]), "+f"(d[10]), "+f"(d[11]), "+f"(d[12]), "+f"(d[13]), "+f"(d[14]), "+f"(d[15]), "+f"(d[16]), "+f"(d[17]), "+f"(d[18]), "+f"(d[19]), "+f"(d[20]), "+f"(d[21]), "+f"(d[22]), "+f"(d[23]), "+f"(d[24]), "+f"(d[25]), "+f"(d[26]), "+f"(d[27]), "+f"(d[28]), "+f"(d[29]), "+f"(d[30]), "+f"(d[31]), "+f"(d[32]), "+f"(d[33]), "+f"(d[34]), "+f"(d[35]), "+f"(d[36]), "+f"(d[37]), "+f"(d[38]), "+f"(d[39]), "+f"(d[40]), "+f"(d[41]), "+f"(d[42]), "+f"(d[43]), "+f"(d[44]), "+f"(d[45]), "+f"(d[46]), "+f"(d[47]), "+f"(d[48]), "+f"(d[49]), "+f"(d[50]), "+f"(d[51]), "+f"(d[52]), "+f"(d[53]), "+f"(d[54]), "+f"(d[55]), "+f"(d[56]), "+f"(d[57]), "+f"(d[58]), "+f"(d[59]), "+f"(d[60]), "+f"(d[61]), "+f"(d[62]), "+f"(d[63])
        : "l"(da), "l"(db), "r"(sd));
}
__device__ __forceinline__ void wg_tt_n64(float (&d)[32], uint64_t da, uint64_t db, int sd) {
    asm volatile("{.reg .pred p; setp.ne.b32 p, %34, 0;\n"
        "wgmma.mma_async.sync.aligned.m64n64k16.f32.bf16.bf16 {%0,%1,%2,%3,%4,%5,%6,%7,%8,%9,%10,%11,%12,%13,%14,%15,%16,%17,%18,%19,%20,%21,%22,%23,%24,%25,%26,%27,%28,%29,%30,%31},%32,%33,p,1,1,1,1;}"
        : "+f"(d[0]), "+f"(d[1]), "+f"(d[2]), "+f"(d[3]), "+f"(d[4]), "+f"(d[5]), "+f"(d[6]), "+f"(d[7]), "+f"(d[8]), "+f"(d[9]), "+f"(d[10]), "+f"(d[11]), "+f"(d[12]), "+f"(d[13]), "+f"(d[14]), "+f"(d[15]), "+f"(d[16]), "+f"(d[17]), "+f"(d[18]), "+f"(d[19]), "+f"(d[20]), "+f"(d[21]), "+f"(d[22]), "+f"(d[23]), "+f"(d[24]), "+f"(d[25]), "+f"(d[26]), "+f"(d[27]), "+f"(d[28]), "+f"(d[29]), "+f"(d[30]), "+f"(d[31])
        : "l"(da), "l"(db), "r"(sd));
}
__device__ __forceinline__ void wg_tt_n8(float (&d)[4], uint64_t da, uint64_t db, int sd) {
    asm volatile("{.reg .pred p; setp.ne.b32 p, %6, 0;\n"
        "wgmma.mma_async.sync.aligned.m64n8k16.f32.bf16.bf16 {%0,%1,%2,%3},%4,%5,p,1,1,1,1;}"
        : "+f"(d[0]), "+f"(d[1]), "+f"(d[2]), "+f"(d[3])
        : "l"(da), "l"(db), "r"(sd));
}


__device__ __forceinline__ float ex2(float x) { float y; asm("ex2.approx.ftz.f32 %0,%1;" : "=f"(y) : "f"(x)); return y; }
__device__ __forceinline__ uint32_t pack_bf(float lo, float hi) { uint32_t r; asm("cvt.rn.bf16x2.f32 %0,%1,%2;" : "=r"(r) : "f"(hi), "f"(lo)); return r; }
__device__ __forceinline__ uint32_t pack_h(float lo, float hi) { uint32_t r; asm("cvt.rn.f16x2.f32 %0,%1,%2;" : "=r"(r) : "f"(hi), "f"(lo)); return r; }
__device__ __forceinline__ float bf_lo(uint32_t v) { return __uint_as_float(v << 16); }
__device__ __forceinline__ float bf_hi(uint32_t v) { return __uint_as_float(v & 0xFFFF0000u); }
__device__ __forceinline__ uint32_t fma_bf2(uint32_t a, uint32_t b, uint32_t c) { uint32_t r; asm("fma.rn.bf16x2 %0,%1,%2,%3;" : "=r"(r) : "r"(a), "r"(b), "r"(c)); return r; }
__device__ __forceinline__ uint32_t add_bf2(uint32_t a, uint32_t b) { uint32_t r; asm("add.rn.bf16x2 %0,%1,%2;" : "=r"(r) : "r"(a), "r"(b)); return r; }
__device__ __forceinline__ uint32_t min_bf2(uint32_t a, uint32_t b) { uint32_t r; asm("min.NaN.bf16x2 %0,%1,%2;" : "=r"(r) : "r"(a), "r"(b)); return r; }
__device__ __forceinline__ void sts32(uint32_t a, uint32_t v) { asm volatile("st.shared.b32 [%0],%1;" ::"r"(a), "r"(v) : "memory"); }
__device__ __forceinline__ void sts128(uint32_t a, uint4 v) { asm volatile("st.shared.v4.b32 [%0],{%1,%2,%3,%4};" ::"r"(a), "r"(v.x), "r"(v.y), "r"(v.z), "r"(v.w) : "memory"); }
__device__ __forceinline__ uint4 lds128(uint32_t a) { uint4 v; asm volatile("ld.shared.v4.b32 {%0,%1,%2,%3},[%4];" : "=r"(v.x), "=r"(v.y), "=r"(v.z), "=r"(v.w) : "r"(a) : "memory"); return v; }
__device__ __forceinline__ uint32_t lds32(uint32_t a) { uint32_t v; asm volatile("ld.shared.b32 %0,[%1];" : "=r"(v) : "r"(a) : "memory"); return v; }
__device__ __forceinline__ void red_v2(float* p, float a, float b) { asm volatile("red.global.add.v2.f32 [%0],{%1,%2};" ::"l"(p), "f"(a), "f"(b) : "memory"); }
__device__ __forceinline__ void mma16816(float (&d)[4], const uint32_t (&a)[4], uint32_t b0, uint32_t b1) {
    asm volatile("mma.sync.aligned.m16n8k16.row.col.f32.bf16.bf16.f32 {%0,%1,%2,%3},{%4,%5,%6,%7},{%8,%9},{%0,%1,%2,%3};"
                 : "+f"(d[0]), "+f"(d[1]), "+f"(d[2]), "+f"(d[3]) : "r"(a[0]), "r"(a[1]), "r"(a[2]), "r"(a[3]), "r"(b0), "r"(b1));
}

__device__ __forceinline__ uint32_t phi2(float a, float b) {
    uint32_t hi;
    asm("cvt.rn.relu.bf16x2.f32 %0,%1,%2;" : "=r"(hi) : "f"(b), "f"(a));
    const uint32_t e = min_bf2(pack_bf(ex2(a * 1.4426950408889634f), ex2(b * 1.4426950408889634f)), 0x3F803F80u);
    return add_bf2(add_bf2(hi, e), 0x35863586u);
}

template <int I> __device__ __forceinline__ uint32_t exp_pair(float a, float b, uint32_t sgn) {
    if (pair_mufu(I)) return pack_bf(ex2(a), ex2(b));
    uint32_t e;
    asm("prmt.b32 %0,%1,%2,0x6521;" : "=r"(e) : "f"(a), "f"(b));
    uint32_t m = e | 0x3F803F80u;
    uint32_t z;
    if (tile_unit(I / 2)) asm("lop3.b32 %0,%1,0x007F007F,%2,0x56;" : "=r"(z) : "r"(e), "r"(sgn));
    else z = e | 0x007F007Fu;
    return fma_bf2(e, m, z);
}

__device__ __noinline__ void slow_rows(float* o, uint4 qv, int lane) {
    const uint32_t q[4] = {qv.x, qv.y, qv.z, qv.w};
    const int g = lane >> 2, tq = lane & 3;
    float m0 = -INFINITY, m1 = -INFINITY, l0 = 0.f, l1 = 0.f;
    float oa[4] = {0.f, 0.f, 0.f, 0.f}, ob[4] = {0.f, 0.f, 0.f, 0.f};
    const uint32_t* kab = reinterpret_cast<const uint32_t*>(g_kabs);
#pragma unroll 1
    for (int it = 0; it < 128; it++) {
        const int t = it >> 2, kb = it & 3;
        float s0[4] = {0.f, 0.f, 0.f, 0.f}, s1[4] = {0.f, 0.f, 0.f, 0.f};
        const int k0 = 32 * (16 * kb + g) + t, k1 = k0 + 256;
        mma16816(s0, q, __ldcg(kab + k0 * 8 + tq), __ldcg(kab + k0 * 8 + 4 + tq));
        mma16816(s1, q, __ldcg(kab + k1 * 8 + tq), __ldcg(kab + k1 * 8 + 4 + tq));
#pragma unroll
        for (int i = 0; i < 4; i++) {
            const uint32_t r = pack_bf(s0[i], s1[i]);
            s0[i] = bf_lo(r) * QSCALE; s1[i] = bf_hi(r) * QSCALE;
        }
        float x0 = fmaxf(fmaxf(s0[0], s0[1]), fmaxf(s1[0], s1[1])), x1 = fmaxf(fmaxf(s0[2], s0[3]), fmaxf(s1[2], s1[3]));
        x0 = fmaxf(x0, __shfl_xor_sync(0xffffffffu, x0, 1)); x0 = fmaxf(x0, __shfl_xor_sync(0xffffffffu, x0, 2));
        x1 = fmaxf(x1, __shfl_xor_sync(0xffffffffu, x1, 1)); x1 = fmaxf(x1, __shfl_xor_sync(0xffffffffu, x1, 2));
        const float n0 = fmaxf(m0, x0), n1 = fmaxf(m1, x1);
        const float c0 = ex2(m0 - n0), c1 = ex2(m1 - n1);
        m0 = n0; m1 = n1;
        uint32_t p[4];
        p[0] = pack_bf(ex2(s0[0] - n0), ex2(s0[1] - n0)); p[1] = pack_bf(ex2(s0[2] - n1), ex2(s0[3] - n1));
        p[2] = pack_bf(ex2(s1[0] - n0), ex2(s1[1] - n0)); p[3] = pack_bf(ex2(s1[2] - n1), ex2(s1[3] - n1));
        l0 = l0 * c0 + (bf_lo(p[0]) + bf_hi(p[0]) + bf_lo(p[2]) + bf_hi(p[2]));
        l1 = l1 * c1 + (bf_lo(p[1]) + bf_hi(p[1]) + bf_lo(p[3]) + bf_hi(p[3]));
        oa[0] *= c0; oa[1] *= c0; ob[0] *= c0; ob[1] *= c0; oa[2] *= c1; oa[3] *= c1; ob[2] *= c1; ob[3] *= c1;
        const unsigned short* vp = reinterpret_cast<const unsigned short*>(g_kv + t * TILE_BYTES + 2048 + kb * 768 + tq * 32) + g;
        const uint32_t v0 = __ldcg(vp) | ((uint32_t)__ldcg(vp + 8) << 16), v1 = __ldcg(vp + 64) | ((uint32_t)__ldcg(vp + 72) << 16);
        const uint32_t v2 = __ldcg(vp + 128) | ((uint32_t)__ldcg(vp + 136) << 16), v3 = __ldcg(vp + 192) | ((uint32_t)__ldcg(vp + 200) << 16);
        mma16816(oa, p, v0, v1);
        mma16816(ob, p, v2, v3);
    }
    l0 += __shfl_xor_sync(0xffffffffu, l0, 1); l0 += __shfl_xor_sync(0xffffffffu, l0, 2);
    l1 += __shfl_xor_sync(0xffffffffu, l1, 1); l1 += __shfl_xor_sync(0xffffffffu, l1, 2);
#pragma unroll
    for (int i = 0; i < 4; i++) { o[i] = oa[i]; o[4 + i] = ob[i]; }
    o[8] = l0; o[9] = l1;
}

template <int J> __device__ __forceinline__ void exp_block(const float (&s)[32], uint32_t (&p)[4], uint32_t sgn) {
    p[0] = exp_pair<4 * J + 0>(s[8 * J + 0], s[8 * J + 1], sgn);
    p[1] = exp_pair<4 * J + 1>(s[8 * J + 2], s[8 * J + 3], sgn);
    p[2] = exp_pair<4 * J + 2>(s[8 * J + 4], s[8 * J + 5], sgn);
    p[3] = exp_pair<4 * J + 3>(s[8 * J + 6], s[8 * J + 7], sgn);
}

__device__ __forceinline__ void scale_q(uint4 q, uint32_t (&qh)[4]) {
    qh[0] = pack_h(bf_lo(q.x) * QSCALE, bf_hi(q.x) * QSCALE); qh[1] = pack_h(bf_lo(q.y) * QSCALE, bf_hi(q.y) * QSCALE);
    qh[2] = pack_h(bf_lo(q.z) * QSCALE, bf_hi(q.z) * QSCALE); qh[3] = pack_h(bf_lo(q.w) * QSCALE, bf_hi(q.w) * QSCALE);
}
__device__ __forceinline__ void norm2(uint32_t a0, uint32_t a1, uint32_t b0, uint32_t b1, float& na, float& nb) {
    const uint32_t sa = fma_bf2(a0, a0, fma_bf2(a1, a1, 0u)), sb = fma_bf2(b0, b0, fma_bf2(b1, b1, 0u));
    uint32_t v = add_bf2(__byte_perm(sa, sb, 0x5410), __byte_perm(sa, sb, 0x7632));
    v = add_bf2(v, __shfl_xor_sync(0xffffffffu, v, 1));
    v = add_bf2(v, __shfl_xor_sync(0xffffffffu, v, 2));
    na = bf_lo(v) * (1.03f * QSCALE * QSCALE);
    nb = bf_hi(v) * (1.03f * QSCALE * QSCALE);
}
__host__ __device__ constexpr int unit_tile(int n) {
    int j = 0;
    for (; j < 8; j++) if (tile_unit(j) && n-- == 0) break;
    return j;
}
static_assert(unit_tile(3) < 8, "the reference max uses four unscaled n8-tiles");
__device__ __forceinline__ float max8(const float* a, const float* b, const float* c, const float* d) {
    return fmaxf(fmaxf(fmaxf(a[0], a[1]), fmaxf(b[0], b[1])), fmaxf(fmaxf(c[0], c[1]), fmaxf(d[0], d[1])));
}
__device__ __forceinline__ void quad_max2(float& x, float& y) {
    uint32_t v = pack_h(x, y), w;
    w = __shfl_xor_sync(0xffffffffu, v, 1); asm("max.NaN.f16x2 %0,%0,%1;" : "+r"(v) : "r"(w));
    w = __shfl_xor_sync(0xffffffffu, v, 2); asm("max.NaN.f16x2 %0,%0,%1;" : "+r"(v) : "r"(w));
    const float2 f = __half22float2(*reinterpret_cast<__half2*>(&v));
    x = f.x; y = f.y;
}
__device__ __forceinline__ float guard_rcp(float n) { return n <= 16777216.f ? rcp(fmaxf(n, 1e-20f)) : -1.f; }
__device__ __forceinline__ float guard_limit(float r0, float r1, float m0, float m1) {
    const float a0 = GUARD - fabsf(m0), a1 = GUARD - fabsf(m1);
    const float l = fminf(a0 * a0 * r0, a1 * a1 * r1);
    return (a0 > 0.f && a1 > 0.f) ? l : -1.f;
}
__device__ __forceinline__ float pair_bias(int i, float m0, float m1) {
    const float m = (i & 1) ? m1 : m0;
    return pair_mufu(i) ? (MUFU_BIAS - m) : (tile_unit(i / 2) ? (256.f + WIN - m) : (512.f + 2.f * WIN - 2.f * m));
}

__device__ __forceinline__ void set_bias(float (&s)[32], float m0, float m1) {
#pragma unroll
    for (int i = 0; i < 16; i++) { const float b = pair_bias(i, m0, m1); s[2 * i] = b; s[2 * i + 1] = b; }
    pin(s);
}

template <int PASS> __device__ __forceinline__ uint4 finish_rows(float (&o)[12], float (&s)[32], bool ok) {
    const int lane = threadIdx.x & 31;
    float l0 = __shfl_sync(0xffffffffu, o[8], lane & ~3), l1 = __shfl_sync(0xffffffffu, o[10], lane & ~3);
    const float chk = ((fabsf(o[0]) + fabsf(o[1])) + (fabsf(o[2]) + fabsf(o[3]))) + ((fabsf(o[4]) + fabsf(o[5])) + (fabsf(o[6]) + fabsf(o[7]))) + (o[8] + o[10]);
    ok = ok && chk <= 1.0e37f;
    if (__any_sync(0xffffffffu, !ok)) {
        float r[10];
        float* park = g_spark + blockIdx.x * 512 + threadIdx.x;
        if (PASS == 0) {
#pragma unroll
            for (int i = 0; i < 32; i++) __stcg(park + i * (NCTA * 512), s[i]);
        }
        slow_rows(r, __ldcg(&g_q[blockIdx.x * 1024 + PASS * 512 + threadIdx.x]), lane);
#pragma unroll
        for (int i = 0; i < 8; i++) o[i] = r[i];
        l0 = r[8]; l1 = r[9];
        if (PASS == 0) {
#pragma unroll
            for (int i = 0; i < 32; i++) s[i] = __ldcg(park + i * (NCTA * 512));
        }
    }
    const float i0 = rcp(l0), i1 = rcp(l1);
    return make_uint4(pack_bf(o[0] * i0, o[1] * i0), pack_bf(o[2] * i1, o[3] * i1), pack_bf(o[4] * i0, o[5] * i0), pack_bf(o[6] * i1, o[7] * i1));
}

__device__ __forceinline__ void gemm_chunk(float (&acc)[64], uint32_t a_addr, uint32_t b_addr, bool first) {
    const uint64_t da = mkdesc(a_addr, 16, 1024, 1), db = mkdesc(b_addr, 8192, 1024, 1);
    wg_fence();
#pragma unroll
    for (int k = 0; k < 4; k++) wg_ss_n128(acc, da + (uint64_t)(k * 2), db + (uint64_t)(k * 128), (first && k == 0) ? 0 : 1);
    wg_commit();
    wg_wait0();
    pin(acc);
}
template <uint32_t BS = 8192> __device__ __forceinline__ void store_tile(uint32_t lane_base, uint32_t lane_x, const uint32_t (&v)[32]) {
#pragma unroll
    for (int j = 0; j < 8; j++) stmatrix4(lane_base + (j >> 2) * BS + ((((j & 3) * 2) << 4) ^ lane_x), v[4 * j], v[4 * j + 1], v[4 * j + 2], v[4 * j + 3]);
}

__host__ __device__ constexpr int chunk_k(int n) { return (n & 7) * 64; }
template <int N> __device__ __forceinline__ void load_a(const Maps& maps, int kofs = 0) {
    mbar_expect(BAR + 8 * (B_FULL + (N & 1)), 8192);
    tma2(SB + SM_AUX + (N & 1) * STAGE_BYTES, N < 24 ? &maps.xB : &maps.oB, chunk_k(N) + kofs, (blockIdx.x >> 2) * 64, BAR + 8 * (B_FULL + (N & 1)));
}
template <int N> __device__ __forceinline__ void load_b(const Maps& maps, int kofs = 0) {
    constexpr uint32_t fb = BAR + 8 * (B_FULL + (N & 1)), dst = SB + SM_AUX + (N & 1) * STAGE_BYTES + 8192;
    mbar_expect(fb, 16384);
    tma3(dst, N < 24 ? &maps.wB : &maps.woB, 0, chunk_k(N) + kofs, (N < 16 ? 8 + (N & 8) : 0) + (blockIdx.x & 3) * 2, fb);
}
__device__ __forceinline__ void send_pass0(bool& sent0, bool force) {
    if (!sent0) {
        if (force) mbar_wait(BAR + 8 * B_OD, 0);
        if (mbar_test(BAR + 8 * B_OD, 0)) {
            sent0 = true;
            if (elect()) red_release(&g_cntOA[blockIdx.x * 8]);
        }
    }
}
template <int N, bool LAST> __device__ __forceinline__ void aux_chunk(float (&acc)[64], const Maps& maps, int wp, unsigned epoch, bool& sent0, int p) {
    constexpr uint32_t st = SB + SM_AUX + (N & 1) * STAGE_BYTES;
    constexpr int M = N + 2;
    mbar_wait(BAR + 8 * (B_FULL + (N & 1)), ((N >> 1) + p) & 1);
    gemm_chunk(acc, st, st + 8192, chunk_k(N) == 0 && p == 0);
    bar_sync(5, 128);
    if (M != 17 && M < 32) {
        if (wp == 0) {
            if (M != 24 && M != 25 && elect()) load_a<M>(maps, p * 128);
        } else if (wp == 1) {
            if (elect()) load_b<M>(maps, p * 128);
        } else if (LAST) {
            if (wp == 2) {
                if (M == 25) send_pass0(sent0, false);
            } else if (M == 8) {
                if (elect()) {
                    l2_prefetch(maps.pwoB + blockIdx.x * 4096, 4096);
                    l2_prefetch(maps.pwoA + blockIdx.x * 4096, 4096);
                }
            } else if (M == 25) {
                if (elect()) {
                    poll_ge<32>(&g_cntKVB[(blockIdx.x & 3) * 32], (epoch + 1) * 32u);
                    fence_async_g();
                    mbar_expect(BAR + 8 * B_KS, 8 * 272 * 4);
                    bulk_load(SB + SM_X, g_kvsum[epoch & 1] + (blockIdx.x & 3) * 8 * 272, 8 * 272 * 4, BAR + 8 * B_KS);
                }
            }
        }
        __syncwarp();
    }
}
template <int N0, int NCH> __device__ __forceinline__ void aux_job(float (&acc)[64], const Maps& maps, int wp, unsigned epoch, bool& sent0) {
    fresh(acc);
#pragma unroll
    for (int p = 0; p < NCH / 2 - 1; p++) {
        aux_chunk<N0, false>(acc, maps, wp, epoch, sent0, p);
        aux_chunk<N0 + 1, false>(acc, maps, wp, epoch, sent0, p);
    }
    aux_chunk<N0 + NCH - 2, true>(acc, maps, wp, epoch, sent0, 0);
    aux_chunk<N0 + NCH - 1, true>(acc, maps, wp, epoch, sent0, 0);
}

#define E_(J) exp_block<J>(s, p##J, sgn); pin(p##J);
#define P_(J) wg_pv_n24<1>(o, p##J, dK + (128 + 48 * J));
#define TILE_SEQ(QK, RESET) E_(0) wg_fence(); P_(0) E_(1) E_(2) wg_fence(); P_(1) P_(2) E_(3) RESET wg_fence(); P_(3) QK
#define TILE_BODY(QK, RESET)                                                                   \
    {                                                                                          \
        uint32_t p0[4], p1[4], p2[4], p3[4];                                                   \
        TILE_SEQ(QK, RESET)                                                             \
        wg_commit();                                                                           \
        wg_wait0();                                                                            \
        pin(s); pin(o);                                                                        \
    }

__global__ void __launch_bounds__(NTHREADS, 1) fused_kernel(const __grid_constant__ Maps maps) {
    extern __shared__ __align__(1024) uint8_t smem[];
    if (threadIdx.x < 128) asm volatile("prefetch.global.L2 [%0];" ::"l"(maps.pxA + blockIdx.x * 16384 + threadIdx.x * 128));
    constexpr uint32_t sb = SB, bar = BAR;
    if ((uint32_t)__cvta_generic_to_shared(smem) != sb) __trap();
    const int tid = threadIdx.x, warp = tid >> 5, lane = tid & 31;
    const int wg = __shfl_sync(0xffffffffu, tid >> 7, 0);
    const int wp = __shfl_sync(0xffffffffu, warp & 3, 0), g = lane >> 2, tq = lane & 3;
    const int cta = blockIdx.x, bi = cta >> 2, bj = cta & 3;

    if (wg == 1 && bj < 2) {
        const uint8_t* src = (bj == 0 ? maps.pwk : maps.pwv) + (tid & 127) * 16;
        const uint32_t dst = sb + SM_WKV + (((tid & 127) * 16) ^ ((tid & 8) << 1));
#pragma unroll
        for (int i = 0; i < 8; i++) asm volatile("cp.async.cg.shared.global [%0],[%1],16;" ::"r"(dst + i * 2048), "l"(src + i * 2048) : "memory");
    }
    if (lane == 0) {
        if (warp >= 8 && warp < 16) {
            const int c = warp - 8;
            mbar_init(bar + 8 * (B_X + c), 1);
            fence_async_s();
            mbar_expect(bar + 8 * (B_X + c), 8192);
            tma2(sb + SM_XA + c * 8192, &maps.xA, c * 64, bi * 64, bar + 8 * (B_X + c));
        } else if (warp == 0) {
            for (int i = B_W0; i < B_FULL; i++) mbar_init(bar + 8 * i, i < B_W0 + 4 ? 2 : 1);
            fence_async_s();
        } else if (warp == 1) {
            for (int i = B_FULL; i < B_END; i++) mbar_init(bar + 8 * i, i < B_KP ? 2 : (i < B_QD ? 4 : 16));
            fence_async_s();
        }
    }
    __syncthreads();
    if (lane == 0) {
        if (warp == 8 || warp == 9) {
            __nanosleep(600);
#pragma unroll
            for (int c = 0; c < 4; c++) {
                mbar_expect(bar + 8 * (B_W0 + c), 16384);
                tma2(sb + (warp == 8 ? SM_WQ0 : SM_AUX) + c * 16384, &maps.wq, bj * 128 + (warp - 8) * 64, c * 128, bar + 8 * (B_W0 + c));
            }
        } else if (warp == 18) {
            unsigned tk;
            asm volatile("atom.global.add.u32 %0,[%1],1;" : "=r"(tk) : "l"(&g_ticket[0]) : "memory");
            sts32(sb + SM_MISC, tk / NCTA);
            mbar_arrive(bar + 8 * B_EP);
        }
    }
    __syncwarp();

    if (wg < 4) {
        const int t7 = tid & 127;
        g_llo[cta * 512 + tid] = make_uint4(0, 0, 0, 0);
        uint4 qraw, q1;
        if (wg == 0) {
            float acc[64];
            fresh(acc);
            mbar_wait(bar + 8 * B_KP, 0);
#pragma unroll
            for (int c = 0; c < 8; c++) {
                mbar_wait(bar + 8 * (B_X + c), 0);
                if ((c & 1) == 0) mbar_wait(bar + 8 * (B_W0 + (c >> 1)), 0);
                wg_fence();
#pragma unroll
                for (int k = 0; k < 4; k++)
                    wg_ss_n128(acc, mkdesc(sb + SM_XA + c * 8192 + k * 32, 16, 1024, 1), mkdesc(sb + SM_WQ0 + c * 8192 + k * 2048, SM_AUX - SM_WQ0, 1024, 1), (c | k) != 0);
                wg_commit();
            }
            wg_wait0();
            pin(acc);
            uint4 v[8];
#pragma unroll
            for (int h = 0; h < 8; h++) {
                v[h] = make_uint4(pack_bf(acc[8 * h], acc[8 * h + 1]), pack_bf(acc[8 * h + 2], acc[8 * h + 3]),
                                  pack_bf(acc[8 * h + 4], acc[8 * h + 5]), pack_bf(acc[8 * h + 6], acc[8 * h + 7]));
                if (h & 3) sts128(sb + SM_QX + (((h & 3) - 1) * 2 + (h >> 2)) * 2048 + t7 * 16, v[h]);
            }
            __syncwarp();
            if (lane == 0) mbar_arrive(bar + 8 * B_QP);
            qraw = v[0];
            q1 = v[4];
        } else {
            if (wg == 1) {
                if (bj < 2) {
                    float acc[8];
                    fresh(acc);
                    asm volatile("cp.async.wait_all;" ::: "memory");
                    fence_async_s();
                    bar_sync(3, 128);
#pragma unroll
                    for (int c = 0; c < 8; c++) {
                        mbar_wait(bar + 8 * (B_X + c), 0);
                        wg_fence();
#pragma unroll
                        for (int k = 0; k < 4; k++)
                            wg_ss_n16(acc, mkdesc(sb + SM_XA + c * 8192 + k * 32, 16, 1024, 1), mkdesc(sb + SM_WKV + c * 2048 + k * 512, 16, 256, 3), (c | k) != 0);
                        wg_commit();
                    }
                    wg_wait0();
                    pin(acc);
                    const int row = wp * 16 + g;
                    sts32(sb + SM_KSCR + row * 32 + tq * 4, pack_bf(acc[0], acc[1]));
                    sts32(sb + SM_KSCR + (row + 8) * 32 + tq * 4, pack_bf(acc[2], acc[3]));
                    sts32(sb + SM_KSCR + row * 32 + 16 + tq * 4, pack_bf(acc[4], acc[5]));
                    sts32(sb + SM_KSCR + (row + 8) * 32 + 16 + tq * 4, pack_bf(acc[6], acc[7]));
                    bar_sync(3, 128);
                    const int tile = t7 >> 2, hf = (t7 >> 1) & 1, slot = 2 * bi + (t7 & 1);
                    const uint32_t ra = sb + SM_KSCR + ((t7 & 1) * 32 + tile) * 32 + hf * 16;
                    const uint4 cur = lds128(ra);
                    uint8_t* tb = g_kv + tile * TILE_BYTES;
                    if (bj == 0) {
                        uint4 prev = make_uint4(0, 0, 0, 0);
                        if (tile != 0) prev = lds128(ra - 32);
                        const float sc = ((MUFU_MASK >> (2 * (bi >> 2))) & 3u) ? 1.f : 2.f;
                        uint4 dd;
                        dd.x = pack_h((bf_lo(cur.x) - bf_lo(prev.x)) * sc, (bf_hi(cur.x) - bf_hi(prev.x)) * sc);
                        dd.y = pack_h((bf_lo(cur.y) - bf_lo(prev.y)) * sc, (bf_hi(cur.y) - bf_hi(prev.y)) * sc);
                        dd.z = pack_h((bf_lo(cur.z) - bf_lo(prev.z)) * sc, (bf_hi(cur.z) - bf_hi(prev.z)) * sc);
                        dd.w = pack_h((bf_lo(cur.w) - bf_lo(prev.w)) * sc, (bf_hi(cur.w) - bf_hi(prev.w)) * sc);
                        *reinterpret_cast<uint4*>(tb + (slot >> 3) * 256 + hf * 128 + (slot & 7) * 16) = dd;
                    } else {
                        uint8_t* vb = tb + 2048 + (slot >> 4) * 768 + (slot & 15) * 16;
                        *reinterpret_cast<uint4*>(vb + hf * 256) = cur;
                        if (hf) *reinterpret_cast<uint4*>(vb + 512) = make_uint4(0x00003F80u, 0u, 0u, 0u);
                    }
                    bar_sync(3, 128);
                    if (lane == 0) mbar_arrive(bar + 8 * B_KP);
                    if (t7 == 0) red_release(&g_cntKV[0]);
                    if (lane == 0) mbar_arrive(bar + 8 * B_KR);
                    __syncwarp();
                    if (bj == 0) {
                        reinterpret_cast<uint4*>(g_kabs)[(bi * 64 + (t7 & 1) * 32 + tile) * 2 + hf] = cur;
                        float nn = bf_lo(cur.x) * bf_lo(cur.x) + bf_hi(cur.x) * bf_hi(cur.x) + bf_lo(cur.y) * bf_lo(cur.y) + bf_hi(cur.y) * bf_hi(cur.y) +
                                   bf_lo(cur.z) * bf_lo(cur.z) + bf_hi(cur.z) * bf_hi(cur.z) + bf_lo(cur.w) * bf_lo(cur.w) + bf_hi(cur.w) * bf_hi(cur.w);
                        nn += __shfl_xor_sync(0xffffffffu, nn, 2);
                        const unsigned mx = __reduce_max_sync(0xffffffffu, __float_as_uint(nn) & 0x7FFFFFFFu);
                        if (lane == 0) g_kmax[bi * 4 + wp] = __uint_as_float(mx);
                        __syncwarp();
                        if (lane == 0) mbar_arrive(bar + 8 * B_Q1);
                    }
                } else if (lane == 0) {
                    mbar_arrive(bar + 8 * B_KP);
                    mbar_arrive(bar + 8 * B_KR);
                }
            }
            __syncwarp();
            mbar_wait(bar + 8 * B_QP, 0);
            qraw = lds128(sb + SM_QX + (wg - 1) * 4096 + t7 * 16);
            q1 = lds128(sb + SM_QX + (wg - 1) * 4096 + 2048 + t7 * 16);
        }
        __syncwarp();
        if (lane == 0) mbar_arrive(bar + 8 * B_QD);
        bar_sync(6 + wg, 128);
        const uint32_t sgn = 0x80008000u | __shfl_sync(0xffffffffu, lane, 0);
        uint32_t qh[4], qn[4];
        float s[32], o[12];
        float lim, limn, mn0, mn1;
        {
            float n0, n1, m0, m1, p0, p1, u4[4][4];
            scale_q(qraw, qh);
            scale_q(q1, qn);
            fresh(s); fresh(u4[0]); fresh(u4[1]); fresh(u4[2]); fresh(u4[3]); pin(qh); pin(qn);
            mbar_wait(bar + 8 * B_KV, 0);
            wg_fence();
            wg_qk_n64<0>(s, qh, mkdesc(sb + SM_KV, 128, 256, 0));
#pragma unroll
            for (int j = 0; j < 4; j++) wg_qk_n8<0>(u4[j], qn, mkdesc(sb + SM_KV + unit_tile(j) * 256, 128, 256, 0));
            wg_commit();
            g_q[cta * 1024 + tid] = qraw;
            g_q[cta * 1024 + 512 + tid] = q1;
            norm2(qraw.x, qraw.z, qraw.y, qraw.w, n0, n1);
            norm2(q1.x, q1.z, q1.y, q1.w, p0, p1);
            float gr[4] = {guard_rcp(n0), guard_rcp(n1), guard_rcp(p0), guard_rcp(p1)};
            pin(gr);
            wg_wait0();
            pin(s); pin(u4[0]); pin(u4[1]); pin(u4[2]); pin(u4[3]);
            m0 = max8(s + 4 * unit_tile(0), s + 4 * unit_tile(1), s + 4 * unit_tile(2), s + 4 * unit_tile(3));
            m1 = max8(s + 4 * unit_tile(0) + 2, s + 4 * unit_tile(1) + 2, s + 4 * unit_tile(2) + 2, s + 4 * unit_tile(3) + 2);
            mn0 = max8(u4[0], u4[1], u4[2], u4[3]);
            mn1 = max8(u4[0] + 2, u4[1] + 2, u4[2] + 2, u4[3] + 2);
            quad_max2(m0, mn0);
            quad_max2(m1, mn1);
#pragma unroll
            for (int i = 0; i < 16; i++) { const float b = pair_bias(i, m0, m1); s[2 * i] += b; s[2 * i + 1] += b; }
            lim = guard_limit(gr[0], gr[1], m0, m1);
            limn = guard_limit(gr[2], gr[3], mn0, mn1);
        }
#define TILE_LOOP(T0, T1)                                                                      \
        {                                                                                      \
            bar_sync(6 + wg, 128);     \
            uint64_t dK = mkdesc(__shfl_sync(0xffffffffu, sb + SM_KV + (T0) * TILE_BYTES, 0), 128, 256, 0); \
            _Pragma("unroll 2") for (int t = (T0); t < (T1); t++) {                         \
                TILE_BODY(wg_qk_n64<1>(s, qh, dK + (TILE_BYTES >> 4));, )                      \
                dK += TILE_BYTES >> 4;                                                         \
            }                                                                                  \
        }
#pragma unroll
        for (int i = 0; i < 12; i++) o[i] = 0.f;
        pin(s); pin(o);
        {
            const uint64_t dK = mkdesc(sb + SM_KV, 128, 256, 0);
            TILE_BODY(wg_qk_n64<1>(s, qh, dK + (TILE_BYTES >> 4));, )
        }
        mbar_wait(bar + 8 * (B_KV + 1), 0);
        TILE_LOOP(1, 7)
        mbar_wait(bar + 8 * (B_KV + 2), 0);
        mbar_wait(bar + 8 * B_KM, 0);
        const uint4 kk = lds128(sb + SM_KMAX + lane * 16);
        const float km = __uint_as_float(__reduce_max_sync(0xffffffffu, max(max(kk.x, kk.y), max(kk.z, kk.w))));
        const bool ok0 = km <= fminf(lim, 1048576.f), ok1 = km <= fminf(limn, 1048576.f);
        TILE_LOOP(7, 31)
#pragma unroll
        for (int i = 0; i < 4; i++) qh[i] = qn[i];
        pin(qh);
        {
            const uint64_t dK = mkdesc(sb + SM_KV + 31 * TILE_BYTES, 128, 256, 0);
            TILE_BODY(wg_qk_n64<1>(s, qh, mkdesc(sb + SM_KV, 128, 256, 0));, set_bias(s, mn0, mn1);)
        }
        {
            const uint4 ov = finish_rows<0>(o, s, ok0);
            uint32_t* dst = reinterpret_cast<uint32_t*>(g_oA + (size_t)(bi * 64 + wp * 16 + g) * 512 + bj * 128 + wg * 16 + tq * 2);
            dst[0] = ov.x; dst[8 * 256] = ov.y; dst[4] = ov.z; dst[8 * 256 + 4] = ov.w;
            __syncwarp();
            if (lane == 0) mbar_arrive(bar + 8 * B_OD);
        }
#pragma unroll
        for (int i = 0; i < 12; i++) o[i] = 0.f;
        pin(s); pin(o);
        {
            const uint64_t dK = mkdesc(sb + SM_KV, 128, 256, 0);
            TILE_BODY(wg_qk_n64<1>(s, qh, dK + (TILE_BYTES >> 4));, )
        }
        TILE_LOOP(1, 27)
        if (lane == 0) mbar_arrive(bar + 8 * B_HF);
        bar_sync(1, 512);
        TILE_LOOP(27, 31)
        {
            const uint64_t dK = mkdesc(sb + SM_KV + 31 * TILE_BYTES, 128, 256, 0);
            TILE_BODY(, )
        }
        {
            const uint4 ov = finish_rows<1>(o, s, ok1);
            ll_store(&g_llo[cta * 512 + tid], ov);
            __syncwarp();
            if (lane == 0 && wg == 3) mbar_arrive(bar + 8 * B_F3);
            const uint4* src = &g_llo[(cta & ~3) * 512 + tid];
            const uint32_t dst = sb + SM_T1A + (wp * 16 + ((lane >> 3) & 1) * 8 + (lane & 7)) * 128 + (((wg * 2 + (lane >> 4)) ^ (lane & 7)) << 4);
            mbar_wait(bar + 8 * B_PC, 0);
            uint4 pv[3];
#pragma unroll
            for (int cc = 1; cc < 4; cc++) pv[cc - 1] = ll_load(src + ((bj + cc) & 3) * 512);
            stmatrix4(dst, ov.x, ov.y, ov.z, ov.w);
            fence_async_s();
            __syncwarp();
            if (lane == 0) mbar_arrive(bar + 8 * B_TA);
            unsigned todo = 7;
            for (int it = 0;; it++) {
#pragma unroll
                for (int cc = 1; cc < 4; cc++) {
                    if ((todo >> (cc - 1) & 1) && !__any_sync(0xffffffffu, ll_empty(pv[cc - 1]))) {
                        todo &= ~(1u << (cc - 1));
                        stmatrix4(dst + cc * 8192, ~pv[cc - 1].x, ~pv[cc - 1].y, ~pv[cc - 1].z, ~pv[cc - 1].w);
                        fence_async_s();
                        __syncwarp();
                        if (lane == 0) mbar_arrive(bar + 8 * (B_TA + cc));
                    }
                }
                if (!todo) break;
                if (it > (1 << 22)) __trap();
                __nanosleep(20);
#pragma unroll
                for (int cc = 1; cc < 4; cc++)
                    if (todo >> (cc - 1) & 1) pv[cc - 1] = ll_load(src + ((bj + cc) & 3) * 512);
            }
        }
    } else {
        const int t4 = tid - 512;
        mbar_wait(bar + 8 * B_EP, 0);
        const unsigned epoch = lds32(sb + SM_MISC);
        if (lane == 0) {
            if (wp == 3) {
                poll_ge<20>(&g_cntKV[0], (epoch + 1) * 64u);
                mbar_wait(bar + 8 * B_KR, 0);
                fence_async_g();
                mbar_expect(bar + 8 * B_KV, 2 * TILE_BYTES);
                bulk_load(sb + SM_KV, g_kv, 2 * TILE_BYTES, bar + 8 * B_KV);
                mbar_expect(bar + 8 * (B_KV + 1), 6 * TILE_BYTES);
                bulk_load(sb + SM_KV + 2 * TILE_BYTES, g_kv + 2 * TILE_BYTES, 2 * TILE_BYTES, bar + 8 * (B_KV + 1));
                mbar_wait(bar + 8 * B_KV, 0);
                mbar_wait(bar + 8 * B_QD, 0);
                bulk_load(sb + SM_KV + CHUNK_BYTES, g_kv + CHUNK_BYTES, CHUNK_BYTES, bar + 8 * (B_KV + 1));
                mbar_wait(bar + 8 * (B_KV + 1), 0);
                mbar_expect(bar + 8 * (B_KV + 2), 6 * CHUNK_BYTES);
                for (int c = 2; c < 8; c += 2) bulk_load(sb + SM_KV + c * CHUNK_BYTES, g_kv + c * CHUNK_BYTES, 2 * CHUNK_BYTES, bar + 8 * (B_KV + 2));
            } else if (wp == 2) {
                mbar_wait(bar + 8 * (B_X + 7), 0);
                mbar_wait(bar + 8 * B_KR, 0);
                l2_prefetch(maps.pxB + cta * 16384, 16384);
                l2_prefetch(maps.pwB + cta * 12288, 12288);
                if (bj == 0) {
                    mbar_wait(bar + 8 * B_Q1, 0);
                    red_release(&g_cntKV[32]);
                }
                poll_ge<64>(&g_cntKV[32], (epoch + 1) * 32u);
                fence_async_g();
                mbar_expect(bar + 8 * B_KM, 512);
                bulk_load(sb + SM_KMAX, g_kmax, 512, bar + 8 * B_KM);
            } else {
                mbar_wait(bar + 8 * B_QP, 0);
                mbar_wait(bar + 8 * B_KV, 0);
                if (wp == 0) { load_a<0>(maps); load_a<1>(maps); }
                else { load_b<0>(maps); load_b<1>(maps); }
            }
        }
        __syncwarp();
        const uint32_t st_row = (wp * 16 + ((lane >> 3) & 1) * 8 + (lane & 7)) * 128, st_x = ((lane >> 4) ^ (lane & 7)) << 4;
        float acc[64];
        bool sent0 = false;
        aux_job<0, 8>(acc, maps, wp, epoch, sent0);
        {
            uint32_t v[32];
#pragma unroll
            for (int i = 0; i < 32; i++) v[i] = phi2(acc[2 * i], acc[2 * i + 1]);
            store_tile(sb + SM_X + st_row, st_x, v);
        }
        aux_job<8, 8>(acc, maps, wp, epoch, sent0);
        const uint32_t vt = sb + SM_AUX + STAGE_BYTES;
        {
            uint32_t v[32];
#pragma unroll
            for (int i = 0; i < 32; i++) v[i] = pack_bf(acc[2 * i], acc[2 * i + 1]);
            store_tile(vt + st_row, st_x, v);
        }
        fence_async_s();
        bar_sync(5, 128);
        mbar_wait(bar + 8 * B_KV, 0);
        float* kvsum = g_kvsum[epoch & 1];
        if (t4 < 68) g_kvsum[(epoch + 1) & 1][cta * 68 + t4] = 0.f;
        {
            float kv[2][32], z[2][4], e[2][8];
            fresh(kv[0]); fresh(kv[1]);
            wg_fence();
#pragma unroll
            for (int hb = 0; hb < 2; hb++)
#pragma unroll
                for (int k = 0; k < 4; k++)
                    wg_tt_n64(kv[hb], mkdesc(sb + SM_X + hb * 8192 + k * 2048, 8192, 1024, 1), mkdesc(vt + hb * 8192 + k * 2048, 8192, 1024, 1), k != 0);
            wg_commit();
            wg_wait0();
            pin(kv[0]); pin(kv[1]);
#define KVSEL(W) _Pragma("unroll") for (int i = 0; i < 8; i++) { e[0][i] = kv[0][8 * W + i]; e[1][i] = kv[1][8 * W + i]; } pin(e[0]); pin(e[1]);
            if (wp == 0) { KVSEL(0) } else if (wp == 1) { KVSEL(1) } else if (wp == 2) { KVSEL(2) } else { KVSEL(3) }
            pin(e[0]); pin(e[1]);
            fresh(z[0]); fresh(z[1]);
            wg_fence();
#pragma unroll
            for (int hb = 0; hb < 2; hb++)
#pragma unroll
                for (int k = 0; k < 4; k++)
                    wg_tt_n8(z[hb], mkdesc(sb + SM_X + hb * 8192 + k * 2048, 8192, 1024, 1), mkdesc(sb + SM_KV + 2048 + 512, 128, 256, 0), k != 0);
            wg_commit();
            float* dst = kvsum + (bj * 8 + wp) * 272;
#pragma unroll
            for (int hb = 0; hb < 2; hb++) {
                red_v2(dst + hb * 1088 + g * 16 + tq * 2, e[hb][0], e[hb][1]);
                red_v2(dst + hb * 1088 + (g + 8) * 16 + tq * 2, e[hb][2], e[hb][3]);
                red_v2(dst + hb * 1088 + g * 16 + 8 + tq * 2, e[hb][4], e[hb][5]);
                red_v2(dst + hb * 1088 + (g + 8) * 16 + 8 + tq * 2, e[hb][6], e[hb][7]);
            }
            wg_wait0();
            pin(z[0]); pin(z[1]);
            if (tq == 0) {
                atomicAdd(dst + 256 + g, z[0][0]); atomicAdd(dst + 256 + g + 8, z[0][2]);
                atomicAdd(dst + 1088 + 256 + g, z[1][0]); atomicAdd(dst + 1088 + 256 + g + 8, z[1][2]);
            }
        }
        bar_sync(5, 128);
        if (lane == 0) {
            if (wp == 0) load_a<17>(maps);
            else if (wp == 1) load_b<17>(maps);
            else if (wp == 3) red_release(&g_cntKVB[bj * 32]);
        }
        __syncwarp();
        aux_job<16, 8>(acc, maps, wp, epoch, sent0);
        {
            {
                uint32_t v[32];
#pragma unroll
                for (int i = 0; i < 32; i++) v[i] = phi2(acc[2 * i], acc[2 * i + 1]);
                store_tile<STAGE_BYTES>(sb + SM_AUX + st_row, st_x, v);
            }
            if (wp == 2) send_pass0(sent0, false);
            mbar_wait(bar + 8 * B_KS, 0);
            {
                const int h = t4 >> 4, d = t4 & 15;
                const uint32_t src = sb + SM_X + h * 1088 + d * 64, a = sb + SM_X + 9216 + h * 768 + d * 16;
#pragma unroll
                for (int u = 0; u < 2; u++) {
                    const uint4 a0 = lds128(src + u * 32), a1 = lds128(src + u * 32 + 16);
                    sts128(a + u * 256, make_uint4(pack_bf(__uint_as_float(a0.x), __uint_as_float(a0.y)), pack_bf(__uint_as_float(a0.z), __uint_as_float(a0.w)),
                                                   pack_bf(__uint_as_float(a1.x), __uint_as_float(a1.y)), pack_bf(__uint_as_float(a1.z), __uint_as_float(a1.w))));
                }
                const float zz = __uint_as_float(lds32(sb + SM_X + h * 1088 + 1024 + d * 4));
                const uint32_t z2 = (h & 1) ? pack_bf(0.f, zz) : pack_bf(zz, 0.f);
                sts128(a + 512, make_uint4((h >> 1) == 0 ? z2 : 0u, (h >> 1) == 1 ? z2 : 0u, (h >> 1) == 2 ? z2 : 0u, (h >> 1) == 3 ? z2 : 0u));
            }
            fence_async_s();
            bar_sync(5, 128);
            float num[8][8], den[4];
#pragma unroll
            for (int h = 0; h < 8; h++) fresh(num[h]);
            fresh(den);
            wg_fence();
#pragma unroll
            for (int h = 0; h < 8; h++) {
                const uint64_t da = mkdesc(sb + SM_AUX + (h >> 2) * STAGE_BYTES + (h & 3) * 32, 16, 1024, 1);
                wg_ss_n16(num[h], da, mkdesc(sb + SM_X + 9216 + h * 768, 128, 256, 0), 0);
                wg_ss_n8(den, da, mkdesc(sb + SM_X + 9216 + h * 768 + 512, 128, 256, 0), h != 0);
            }
            wg_commit();
            wg_wait0();
#pragma unroll
            for (int h = 0; h < 8; h++) pin(num[h]);
            pin(den);
            bar_sync(5, 128);
#pragma unroll
            for (int i = 0; i < 4; i++) den[i] = rcp(den[i] + 1e-6f);
#pragma unroll
            for (int h = 0; h < 8; h++) {
                const float i0 = __shfl_sync(0xffffffffu, den[h & 1], (lane & ~3) | (h >> 1));
                const float i1 = __shfl_sync(0xffffffffu, den[2 + (h & 1)], (lane & ~3) | (h >> 1));
                stmatrix4(sb + SM_AUX + st_row + (h >> 2) * STAGE_BYTES + ((((h & 3) * 2) << 4) ^ st_x), pack_bf(num[h][0] * i0, num[h][1] * i0),
                          pack_bf(num[h][2] * i1, num[h][3] * i1), pack_bf(num[h][4] * i0, num[h][5] * i0), pack_bf(num[h][6] * i1, num[h][7] * i1));
            }
            fence_async_s();
            if (wp == 2) send_pass0(sent0, true);
            bar_sync(5, 128);
            if (wp == 0) {
                if (lane == 0) {
                    tma2_store(&maps.oB, bj * 128, bi * 64, sb + SM_AUX);
                    tma2_store(&maps.oB, bj * 128 + 64, bi * 64, sb + SM_AUX + STAGE_BYTES);
                    bulk_wait_all();
                    fence_async_g();
                    red_release(&g_cntOB[cta * 8]);
                }
                __syncwarp();
                if (lane < 4) poll_ge<32>(&g_cntOB[(bi * 4 + lane) * 8], epoch + 1);
                __syncwarp();
                if (lane == 0) {
                    fence_async_g();
                    load_a<24>(maps);
                    load_a<25>(maps);
                }
            } else if (wp == 3) {
                if (lane < 4) poll_ge<32>(&g_cntOA[(bi * 4 + lane) * 8], epoch + 1);
                __syncwarp();
                if (lane == 0) mbar_arrive(bar + 8 * B_PC);
            }
            __syncwarp();
        }
        aux_job<24, 8>(acc, maps, wp, epoch, sent0);
        if (t4 == 64) {
            mbar_expect(bar + 8 * B_TW, 65536);
            for (int c = 0; c < 3; c++) tma3(sb + SM_AUX + c * 16384, &maps.woA, 0, ((bj + c) & 3) * 128 + 64, bj * 2, bar + 8 * B_TW);
        }
        __syncwarp();
        {
            uint32_t v[32];
#pragma unroll
            for (int i = 0; i < 32; i++) v[i] = pack_bf(acc[2 * i], acc[2 * i + 1]);
            store_tile(sb + SM_X + st_row, st_x, v);
            fence_async_s();
            bar_sync(5, 128);
        }
        if (t4 == 64) {
            tma3_store(&maps.out, 0, bi * 64, 8 + bj * 2, sb + SM_X);
            asm volatile("cp.async.bulk.wait_group.read 0;" ::: "memory");
            tma3(sb + SM_X, &maps.woA, 0, ((bj + 3) & 3) * 128 + 64, bj * 2, bar + 8 * B_TW);
        } else if (t4 == 96) {
            mbar_wait(bar + 8 * B_HF, 0);
            fence_async_g();
            mbar_expect(bar + 8 * B_T0, 98304);
            for (int c = 0; c < 4; c++) {
                tma2(sb + SM_T0A + c * 8192, &maps.oA, c * 128, bi * 64, bar + 8 * B_T0);
                tma3(sb + SM_T0W + c * 16384, &maps.woA, 0, c * 128, bj * 2, bar + 8 * B_T0);
            }
        }
        __syncwarp();
        fresh(acc);
        mbar_wait(bar + 8 * B_T0, 0);
        mbar_wait(bar + 8 * B_TW, 0);
        mbar_wait(bar + 8 * B_F3, 0);
        wg_fence();
#pragma unroll
        for (int k = 0; k < 16; k++)
            wg_ss_n128(acc, mkdesc(sb + SM_T0A + (k >> 2) * 8192 + (k & 3) * 32, 16, 1024, 1), mkdesc(sb + SM_T0W + (k >> 2) * 16384 + (k & 3) * 2048, 8192, 1024, 1), k != 0);
        wg_commit();
#pragma unroll
        for (int cc = 0; cc < 4; cc++) {
            mbar_wait(bar + 8 * (B_TA + cc), 0);
            wg_fence();
#pragma unroll
            for (int k = 0; k < 4; k++)
                wg_ss_n128(acc, mkdesc(sb + SM_T1A + cc * 8192 + k * 32, 16, 1024, 1), mkdesc(sb + SM_AUX + cc * 16384 + k * 2048, 8192, 1024, 1), 1);
            wg_commit();
        }
        wg_wait0();
        pin(acc);
        {
            uint32_t v[32];
#pragma unroll
            for (int i = 0; i < 32; i++) v[i] = pack_bf(acc[2 * i], acc[2 * i + 1]);
            store_tile(sb + SM_TO + st_row, st_x, v);
            fence_async_s();
            bar_sync(5, 128);
            if (t4 == 0) {
                tma3_store(&maps.out, 0, bi * 64, bj * 2, sb + SM_TO);
                asm volatile("cp.async.bulk.wait_group.read 0;" ::: "memory");
            }
        }
    }
}

typedef CUresult (*EncodeFn)(CUtensorMap*, CUtensorMapDataType, cuuint32_t, void*, const cuuint64_t*, const cuuint64_t*, const cuuint32_t*,
                             const cuuint32_t*, CUtensorMapInterleave, CUtensorMapSwizzle, CUtensorMapL2promotion, CUtensorMapFloatOOBfill);

void encode(EncodeFn fn, CUtensorMap* m, const void* p, int rank, const cuuint64_t* dims, const cuuint64_t* strides, const cuuint32_t* box, CUtensorMapSwizzle sw) {
    const cuuint32_t es[5] = {1, 1, 1, 1, 1};
    fn(m, CU_TENSOR_MAP_DATA_TYPE_BFLOAT16, (cuuint32_t)rank, const_cast<void*>(p), dims, strides, box, es, CU_TENSOR_MAP_INTERLEAVE_NONE, sw,
       CU_TENSOR_MAP_L2_PROMOTION_L2_256B, CU_TENSOR_MAP_FLOAT_OOB_FILL_NONE);
}
void map_rows(EncodeFn fn, CUtensorMap* m, const void* p) {
    const cuuint64_t d[2] = {512, 2048}, s[1] = {1024};
    const cuuint32_t b[2] = {64, 64};
    encode(fn, m, p, 2, d, s, b, CU_TENSOR_MAP_SWIZZLE_128B);
}
void map_w(EncodeFn fn, CUtensorMap* m, const void* p, int ncols) {
    const cuuint64_t d[3] = {64, 512, (cuuint64_t)ncols / 64}, s[2] = {(cuuint64_t)ncols * 2, 128};
    const cuuint32_t b[3] = {64, 64, 2};
    encode(fn, m, p, 3, d, s, b, CU_TENSOR_MAP_SWIZZLE_128B);
}

}

extern "C" void kernel_launch(void* const* d_in, const int* in_sizes, int n_in, void* d_out, int out_size) {
    static Maps maps;
    static const void* cached[9] = {nullptr};
    bool same = cached[8] == d_out;
    for (int i = 0; i < 8; i++) same = same && cached[i] == d_in[i];
    if (!same) {
        void* f = nullptr;
        cudaDriverEntryPointQueryResult qr;
        cudaGetDriverEntryPoint("cuTensorMapEncodeTiled", &f, cudaEnableDefault, &qr);
        EncodeFn fn = (EncodeFn)f;
        void *oA, *oB;
        cudaGetSymbolAddress(&oA, g_oA);
        cudaGetSymbolAddress(&oB, g_oB);
        map_rows(fn, &maps.xA, d_in[0]);
        {
            const cuuint64_t d[2] = {512, 512}, s[1] = {1024};
            const cuuint32_t b[2] = {64, 128};
            encode(fn, &maps.wq, d_in[1], 2, d, s, b, CU_TENSOR_MAP_SWIZZLE_128B);
        }
        maps.pxA = (const uint8_t*)d_in[0];
        maps.pwk = (const uint8_t*)d_in[2];
        maps.pwv = (const uint8_t*)d_in[3];
        map_w(fn, &maps.woA, d_in[4], 512);
        map_rows(fn, &maps.xB, d_in[5]);
        map_w(fn, &maps.wB, d_in[6], 1536);
        map_w(fn, &maps.woB, d_in[7], 512);
        map_rows(fn, &maps.oA, oA);
        map_rows(fn, &maps.oB, oB);
        {
            const cuuint64_t d2[3] = {64, 2048, 16}, st2[2] = {2048, 128};
            const cuuint32_t b[3] = {64, 64, 2};
            encode(fn, &maps.out, d_out, 3, d2, st2, b, CU_TENSOR_MAP_SWIZZLE_128B);
        }
        maps.pwoA = (const uint8_t*)d_in[4];
        maps.pxB = (const uint8_t*)d_in[5];
        maps.pwB = (const uint8_t*)d_in[6];
        maps.pwoB = (const uint8_t*)d_in[7];
        cudaFuncSetAttribute(fused_kernel, cudaFuncAttributeMaxDynamicSharedMemorySize, SM_TOTAL);
        for (int i = 0; i < 8; i++) cached[i] = d_in[i];
        cached[8] = d_out;
    }
    fused_kernel<<<NCTA, NTHREADS, SM_TOTAL>>>(maps);
}
```
